```python
import torch

def _softmax(x, axis=-1):
    return torch.softmax(x, dim=axis)

def _gelu(x):
    return torch.nn.functional.gelu(x, approximate='tanh')

def _silu(x):
    return torch.nn.functional.silu(x)

def _sigmoid(x):
    return torch.sigmoid(x)

def _layernorm(x, axis=-1, eps=1e-05):
    m = x.mean(dim=axis, keepdim=True)
    v = x.var(dim=axis, keepdim=True, unbiased=False)
    return (x - m) / torch.sqrt(v + eps)

def _scatter_add(tgt, idx, src, axis=0):
    return tgt.clone().index_add_(axis, idx, src)

def _segment_sum(src, seg, n):
    out = torch.zeros((n,) + src.shape[1:], dtype=src.dtype)
    return out.index_add_(0, seg, src)

def _pad(x, pw):
    flat = tuple((v for pair in reversed(pw) for v in pair))
    return torch.nn.functional.pad(x, flat)
kernel_name = 'recurrent_scan__ssm_conv_h3__mixer_gmlp__prompt'

def setup_inputs():

    _w = lambda a: (lambda t: t.to(torch.bfloat16) if t.is_floating_point() else t)(torch.as_tensor(a))

    def _A_setup():
        B, S, D = (1, 2048, 448)
        ks = 4
        return {'q': _w((lambda *s: torch.randn(*s, dtype=torch.bfloat16) * 0.05)(B, S, D)), 'k': _w((lambda *s: torch.randn(*s, dtype=torch.bfloat16) * 0.2)(B, S, D)), 'v': _w((lambda *s: torch.randn(*s, dtype=torch.bfloat16) * 0.2)(B, S, D)), 'shift_k': _w((lambda *s: torch.randn(*s, dtype=torch.bfloat16) * 0.2)(D, ks) * 0.5), 'ssm_k': _w((lambda *s: torch.randn(*s, dtype=torch.bfloat16) * 0.2)(D, S) * (1.0 / S ** 0.5)), 'ssm_D': _w((lambda *s: torch.randn(*s, dtype=torch.bfloat16) * 0.2)(D))}
    _A_in = _A_setup()

    def _B_setup():
        B, S, D, F = (1, 2048, 448, 1792)
        Fh = F // 2
        return {'x': _w((lambda *s: torch.randn(*s, dtype=torch.bfloat16) * 0.05)(B, S, D)), 'w_in': _w((lambda *s: torch.randn(*s, dtype=torch.bfloat16) * 0.8)(D, 2 * Fh)), 'w_sp': _w(0.01 * (lambda *s: torch.randn(*s, dtype=torch.bfloat16) * 0.8)(S, S)), 'b_sp': _w(1.0 + 0.01 * (lambda *s: torch.randn(*s, dtype=torch.bfloat16) * 0.1)(S)), 'w_out': _w((lambda *s: torch.randn(*s, dtype=torch.bfloat16) * 0.1)(Fh, D))}
    _B_in = _B_setup()
    return {'A_q': _A_in['q'], 'A_k': _A_in['k'], 'A_v': _A_in['v'], 'A_shift_k': _A_in['shift_k'], 'A_ssm_k': _A_in['ssm_k'], 'A_ssm_D': _A_in['ssm_D'], 'B_x': _B_in['x'], 'B_w_in': _B_in['w_in'], 'B_w_sp': _B_in['w_sp'], 'B_b_sp': _B_in['b_sp'], 'B_w_out': _B_in['w_out']}

def reference(A_q, A_k, A_v, A_shift_k, A_ssm_k, A_ssm_D, B_x, B_w_in, B_w_sp, B_b_sp, B_w_out):

    def _A_ref(q, k, v, shift_k, ssm_k, ssm_D):
        B, S, D = q.shape
        ks = shift_k.shape[-1]
        k_pad = _pad(k, ((0, 0), (ks - 1, 0), (0, 0)))
        k_shift = torch.zeros_like(k)
        for t in range(ks):
            k_shift = k_shift + k_pad[:, t:t + S, :] * shift_k[:, ks - 1 - t][None, None, :]
        kv = k_shift * v
        L = 2 * S
        kv_pad = _pad(kv, ((0, 0), (0, S), (0, 0)))
        kf_pad = _pad(ssm_k, ((0, 0), (0, S)))
        kv_f = (lambda x, axes=(-2, -1): torch.fft.rfft2(x.float(), dim=axes))(kv_pad[:, None, :, :], axes=(1, 2))
        kf_f = (lambda x, axes=(-2, -1): torch.fft.rfft2(x.float(), dim=axes))(kf_pad[:, None, :], axes=(1, 2))
        kf_f = (lambda x, *d: x.permute(*d))(kf_f, 1, 2, 0)
        y_f = kv_f * kf_f[None, :, :, :]
        y = (lambda x, s, axes=(-2, -1): torch.fft.irfft2(x, s=s, dim=axes).to(torch.bfloat16))(y_f, (1, L), axes=(1, 2))[:, 0, :S, :]
        y = y + kv * ssm_D[None, None, :]
        return q * y

    def _B_ref(x, w_in, w_sp, b_sp, w_out):
        B, S, D = x.shape
        F = w_in.shape[-1]
        Fh = F // 2
        z = _gelu(torch.einsum('bsd,df->bsf', x, w_in))
        z1 = z[..., :Fh].clone()
        z2 = _layernorm(z[..., Fh:], axis=-1)
        g = torch.einsum('ts,bsf->btf', w_sp, z2) + b_sp[None, :, None]
        return torch.einsum('bsf,fd->bsd', z1 * g, w_out)
    x = A_q
    xn = _layernorm(x, axis=-1)
    s = _A_ref(xn, A_k, A_v, A_shift_k, A_ssm_k, A_ssm_D)
    g = _silu(_B_ref(xn, B_w_in, B_w_sp, B_b_sp, B_w_out))
    return x + s * g
```

```cpp
#include <cuda_runtime.h>
#include <cuda_bf16.h>
#include <cuda.h>
#include <stdint.h>

typedef __nv_bfloat16 bf16;

namespace {

constexpr int NCONV = 20;
constexpr int SMEM_BYTES = 232448;
constexpr long long SPIN_LIMIT = 8000000;

__device__ uint4 g_z2img[7 * 32 * 1024];
__device__ uint4 g_uimg[16 * 14 * 1024];
__device__ uint4 g_kvimg[448 * 256];
__device__ uint4 g_yimg[448 * 256];
__device__ uint2 g_zstat[16 * 7 * 128];
__device__ uint2 g_xstat[16 * 160];
__device__ uint4 g_w1[7 * 2 * 8 * 32];
constexpr int FS = 8;
__device__ unsigned g_z2flag[7 * 32 * FS];
__device__ unsigned g_kvflag[7 * 16 * FS];
__device__ unsigned g_uflag[16 * 8 * FS];
__device__ unsigned g_cflag[64 * FS];
__device__ unsigned g_epoch[132];
#define TS(i) do {} while (0)
#define TG(i) do {} while (0)
#define TDUMP() do {} while (0)

__device__ __forceinline__ uint32_t smem_u32(const void* p) { return (uint32_t)__cvta_generic_to_shared(p); }
__device__ __forceinline__ void mbar_init(uint32_t bar, uint32_t cnt) { asm volatile("mbarrier.init.shared::cta.b64 [%0], %1;" :: "r"(bar), "r"(cnt) : "memory"); }
__device__ __forceinline__ void mbar_expect_tx(uint32_t bar, uint32_t bytes) { asm volatile("mbarrier.arrive.expect_tx.shared::cta.b64 _, [%0], %1;" :: "r"(bar), "r"(bytes) : "memory"); }
__device__ __forceinline__ void mbar_arrive(uint32_t bar) { asm volatile("mbarrier.arrive.shared::cta.b64 _, [%0];" :: "r"(bar) : "memory"); }
__device__ __forceinline__ bool mbar_try_wait(uint32_t bar, uint32_t parity) {
  uint32_t ok;
  asm volatile("{\n.reg .pred p;\nmbarrier.try_wait.parity.shared::cta.b64 p, [%1], %2;\nselp.u32 %0, 1, 0, p;\n}" : "=r"(ok) : "r"(bar), "r"(parity) : "memory");
  return ok;
}
__device__ __forceinline__ bool mbar_test(uint32_t bar, uint32_t parity) {
  uint32_t ok;
  asm volatile("{\n.reg .pred p;\nmbarrier.test_wait.parity.shared::cta.b64 p, [%1], %2;\nselp.u32 %0, 1, 0, p;\n}" : "=r"(ok) : "r"(bar), "r"(parity) : "memory");
  return ok;
}
__device__ __forceinline__ bool timed_out(long long tstart) { return clock64() - tstart > SPIN_LIMIT; }
__device__ __forceinline__ void mbar_wait(uint32_t bar, uint32_t parity, long long tstart) {
  if (mbar_try_wait(bar, parity)) return;
  #pragma unroll 1
  for (int i = 0; !mbar_try_wait(bar, parity); i++) { if ((i & 63) == 63 && timed_out(tstart)) break; }
}
__device__ __forceinline__ bool elect_one() {
  uint32_t p; asm volatile("{\n.reg .pred e;\nelect.sync _|e, 0xffffffff;\nselp.u32 %0, 1, 0, e;\n}" : "=r"(p)); return p;
}
__device__ __forceinline__ void tma_load_2d(uint32_t dst, const CUtensorMap* tm, uint32_t bar, int c0, int c1) {
  asm volatile("cp.async.bulk.tensor.2d.shared::cluster.global.mbarrier::complete_tx::bytes [%0], [%1, {%3, %4}], [%2];" :: "r"(dst), "l"(tm), "r"(bar), "r"(c0), "r"(c1) : "memory");
}
__device__ __forceinline__ void tma_load_3d(uint32_t dst, const CUtensorMap* tm, uint32_t bar, int c0, int c1, int c2) {
  asm volatile("cp.async.bulk.tensor.3d.shared::cluster.global.mbarrier::complete_tx::bytes [%0], [%1, {%3, %4, %5}], [%2];" :: "r"(dst), "l"(tm), "r"(bar), "r"(c0), "r"(c1), "r"(c2) : "memory");
}
__device__ __forceinline__ void tma_store_2d(const CUtensorMap* tm, uint32_t src, int c0, int c1) {
  asm volatile("cp.async.bulk.tensor.2d.global.shared::cta.bulk_group [%0, {%2, %3}], [%1];" :: "l"(tm), "r"(src), "r"(c0), "r"(c1) : "memory");
}
__device__ __forceinline__ void tma_prefetch_2d(const CUtensorMap* tm, int c0, int c1) {
  asm volatile("cp.async.bulk.prefetch.tensor.2d.L2.global [%0, {%1, %2}];" :: "l"(tm), "r"(c0), "r"(c1) : "memory");
}
__device__ __forceinline__ void tma_prefetch_3d(const CUtensorMap* tm, int c0, int c1, int c2) {
  asm volatile("cp.async.bulk.prefetch.tensor.3d.L2.global [%0, {%1, %2, %3}];" :: "l"(tm), "r"(c0), "r"(c1), "r"(c2) : "memory");
}
__device__ __forceinline__ void bulk_load(uint32_t dst, const void* src, uint32_t bytes, uint32_t bar) {
  asm volatile("cp.async.bulk.shared::cluster.global.mbarrier::complete_tx::bytes [%0], [%1], %2, [%3];" :: "r"(dst), "l"(src), "r"(bytes), "r"(bar) : "memory");
}
__device__ __forceinline__ void sts32(uint32_t a, uint32_t v) { asm volatile("st.shared.u32 [%0], %1;" :: "r"(a), "r"(v) : "memory"); }
__device__ __forceinline__ void prefetch_tmap(const CUtensorMap* tm) { asm volatile("prefetch.tensormap [%0];" :: "l"(tm) : "memory"); }
__device__ __forceinline__ void wgmma_fence() { __syncwarp(); asm volatile("wgmma.fence.sync.aligned;" ::: "memory"); }
__device__ __forceinline__ void wgmma_commit() { asm volatile("wgmma.commit_group.sync.aligned;" ::: "memory"); }
template<int N> __device__ __forceinline__ void wgmma_wait() { asm volatile("wgmma.wait_group.sync.aligned %0;" :: "n"(N) : "memory"); }
__device__ __forceinline__ constexpr uint64_t desc_hi(uint32_t lbo, uint32_t sbo, uint32_t swz) {
  return ((uint64_t)(lbo >> 4) << 16) | ((uint64_t)(sbo >> 4) << 32) | ((uint64_t)swz << 62);
}
__device__ __forceinline__ uint64_t mkdesc(uint32_t addr, uint64_t hi) { return hi | (uint64_t)(addr >> 4); }
__device__ __forceinline__ void bar_sync(int id, int n) { __syncwarp(); asm volatile("bar.sync %0, %1;" :: "r"(id), "r"(n) : "memory"); }
__device__ __forceinline__ void bar_arrive(int id, int n) { __syncwarp(); asm volatile("bar.arrive %0, %1;" :: "r"(id), "r"(n) : "memory"); }
__device__ __forceinline__ uint32_t lds32(uint32_t a) { uint32_t v; asm volatile("ld.shared.u32 %0, [%1];" : "=r"(v) : "r"(a)); return v; }
__device__ __forceinline__ uint2 lds64(uint32_t a) { uint2 v; asm volatile("ld.shared.v2.u32 {%0,%1}, [%2];" : "=r"(v.x), "=r"(v.y) : "r"(a)); return v; }
__device__ __forceinline__ float2 lds64f(uint32_t a) { float2 v; asm volatile("ld.shared.v2.f32 {%0,%1}, [%2];" : "=f"(v.x), "=f"(v.y) : "r"(a)); return v; }
__device__ __forceinline__ uint4 lds128(uint32_t a) { uint4 v; asm volatile("ld.shared.v4.u32 {%0,%1,%2,%3}, [%4];" : "=r"(v.x), "=r"(v.y), "=r"(v.z), "=r"(v.w) : "r"(a)); return v; }
__device__ __forceinline__ float4 lds128f(uint32_t a) { float4 v; asm volatile("ld.shared.v4.f32 {%0,%1,%2,%3}, [%4];" : "=f"(v.x), "=f"(v.y), "=f"(v.z), "=f"(v.w) : "r"(a)); return v; }
__device__ __forceinline__ void sts32f(uint32_t a, float x) { asm volatile("st.shared.f32 [%0], %1;" :: "r"(a), "f"(x) : "memory"); }
__device__ __forceinline__ void sts64f(uint32_t a, float x, float y) { asm volatile("st.shared.v2.f32 [%0], {%1,%2};" :: "r"(a), "f"(x), "f"(y) : "memory"); }
__device__ __forceinline__ void sts128(uint32_t a, uint4 v) { asm volatile("st.shared.v4.u32 [%0], {%1,%2,%3,%4};" :: "r"(a), "r"(v.x), "r"(v.y), "r"(v.z), "r"(v.w) : "memory"); }
__device__ __forceinline__ void sts128f(uint32_t a, float x, float y, float z, float w) { asm volatile("st.shared.v4.f32 [%0], {%1,%2,%3,%4};" :: "r"(a), "f"(x), "f"(y), "f"(z), "f"(w) : "memory"); }
__device__ __forceinline__ void ldsm_x4_t(uint32_t a, uint32_t& r0, uint32_t& r1, uint32_t& r2, uint32_t& r3) {
  asm volatile("ldmatrix.sync.aligned.m8n8.x4.trans.shared.b16 {%0,%1,%2,%3}, [%4];" : "=r"(r0), "=r"(r1), "=r"(r2), "=r"(r3) : "r"(a) : "memory");
}
__device__ __forceinline__ void stsm_x4_t(uint32_t a, uint32_t r0, uint32_t r1, uint32_t r2, uint32_t r3) {
  asm volatile("stmatrix.sync.aligned.m8n8.x4.trans.shared.b16 [%0], {%1,%2,%3,%4};" :: "r"(a), "r"(r0), "r"(r1), "r"(r2), "r"(r3) : "memory");
}
__device__ __forceinline__ uint4 ldg_nc128(const void* p) { uint4 v; asm volatile("ld.global.nc.L1::no_allocate.v4.u32 {%0,%1,%2,%3}, [%4];" : "=r"(v.x), "=r"(v.y), "=r"(v.z), "=r"(v.w) : "l"(p)); return v; }
__device__ __forceinline__ uint4 ldg_cg128(const void* p) { uint4 v; asm volatile("ld.global.cg.v4.u32 {%0,%1,%2,%3}, [%4];" : "=r"(v.x), "=r"(v.y), "=r"(v.z), "=r"(v.w) : "l"(p) : "memory"); return v; }
__device__ __forceinline__ uint32_t ldg_cg32(const void* p) { uint32_t v; asm volatile("ld.global.cg.u32 %0, [%1];" : "=r"(v) : "l"(p) : "memory"); return v; }
__device__ __forceinline__ uint4 ld_relaxed128(const void* p) { uint4 v; asm volatile("ld.relaxed.gpu.global.v4.u32 {%0,%1,%2,%3}, [%4];" : "=r"(v.x), "=r"(v.y), "=r"(v.z), "=r"(v.w) : "l"(p) : "memory"); return v; }
__device__ __forceinline__ uint2 ld_relaxed64(const void* p) { uint2 v; asm volatile("ld.relaxed.gpu.global.v2.u32 {%0,%1}, [%2];" : "=r"(v.x), "=r"(v.y) : "l"(p) : "memory"); return v; }
__device__ __forceinline__ void st_relaxed128(void* p, uint4 v) { asm volatile("st.relaxed.gpu.global.v4.u32 [%0], {%1,%2,%3,%4};" :: "l"(p), "r"(v.x), "r"(v.y), "r"(v.z), "r"(v.w) : "memory"); }
__device__ __forceinline__ void st_relaxed64(void* p, uint2 v) { asm volatile("st.relaxed.gpu.global.v2.u32 [%0], {%1,%2};" :: "l"(p), "r"(v.x), "r"(v.y) : "memory"); }
__device__ __forceinline__ unsigned ld_relaxed32(const unsigned* p) { unsigned v; asm volatile("ld.relaxed.gpu.global.u32 %0, [%1];" : "=r"(v) : "l"(p) : "memory"); return v; }
__device__ __forceinline__ uint32_t lds_acq(uint32_t a) { uint32_t v; asm volatile("ld.acquire.cta.shared.u32 %0, [%1];" : "=r"(v) : "r"(a) : "memory"); return v; }
__device__ __forceinline__ void sts_rel(uint32_t a, uint32_t v) { asm volatile("st.release.cta.shared.u32 [%0], %1;" :: "r"(a), "r"(v) : "memory"); }
__device__ __forceinline__ void fence_acq() { asm volatile("fence.acquire.gpu;" ::: "memory"); }
__device__ __forceinline__ void st_relaxed32(void* p, uint32_t v) { asm volatile("st.relaxed.gpu.global.u32 [%0], %1;" :: "l"(p), "r"(v) : "memory"); }
__device__ __forceinline__ uint32_t tag_enc(float v, uint32_t t6) { return (__float_as_uint(v) & ~63u) | t6; }
__device__ __forceinline__ bool tag_ok(uint32_t v, uint32_t t6) { return (v & 63u) == t6; }
__device__ __forceinline__ bool tag_ok4(uint4 v, uint32_t t6) { return (((v.x ^ t6) | (v.y ^ t6) | (v.z ^ t6) | (v.w ^ t6)) & 63u) == 0; }
__device__ __forceinline__ float tag_val(uint32_t v) { return __uint_as_float(v & ~63u); }
__device__ __forceinline__ unsigned ld_acquire(const unsigned* p) { unsigned v; asm volatile("ld.acquire.gpu.global.u32 %0, [%1];" : "=r"(v) : "l"(p) : "memory"); return v; }
__device__ __forceinline__ void st_release(unsigned* p, unsigned v) { asm volatile("st.release.gpu.global.u32 [%0], %1;" :: "l"(p), "r"(v) : "memory"); }
__device__ __forceinline__ void fence_async_global() { asm volatile("fence.proxy.async.global;" ::: "memory"); }
__device__ __forceinline__ void fence_async_smem() { asm volatile("fence.proxy.async.shared::cta;" ::: "memory"); }
__device__ __forceinline__ uint32_t pack_bf16(float lo, float hi) { uint32_t r; asm("cvt.rn.bf16x2.f32 %0, %1, %2;" : "=r"(r) : "f"(hi), "f"(lo)); return r; }
__device__ __forceinline__ float bf_lo(uint32_t v) { return __uint_as_float(v << 16); }
__device__ __forceinline__ float bf_hi(uint32_t v) { return __uint_as_float(v & 0xffff0000u); }
__device__ __forceinline__ float rbf(float x) { return bf_lo(pack_bf16(x, 0.f)); }
__device__ __forceinline__ uint32_t bmul2(uint32_t a, uint32_t b) { uint32_t d; asm("mul.rn.bf16x2 %0, %1, %2;" : "=r"(d) : "r"(a), "r"(b)); return d; }
__device__ __forceinline__ uint32_t badd2(uint32_t a, uint32_t b) { uint32_t d; asm("add.rn.bf16x2 %0, %1, %2;" : "=r"(d) : "r"(a), "r"(b)); return d; }
__device__ __forceinline__ uint32_t bsub2(uint32_t a, uint32_t b) { uint32_t d; asm("sub.rn.bf16x2 %0, %1, %2;" : "=r"(d) : "r"(a), "r"(b)); return d; }
__device__ __forceinline__ float tanh_ap(float x) { float y; asm("tanh.approx.f32 %0, %1;" : "=f"(y) : "f"(x)); return y; }
__device__ __forceinline__ float gelu_s(float a, float k0, float k1, float hr) {
  float u = a * fmaf(k1, a * a, k0);
  float h = hr * a;
  return fmaf(h, tanh_ap(u), h);
}
__device__ __forceinline__ float silu_f(float x) { float h = 0.5f * x; return fmaf(h, tanh_ap(h), h); }
__device__ __forceinline__ void ln_scalars(float sum, float sumsq, float inv_n, float& mean_b, float& rsd) {
  float mean = sum * inv_n;
  float var = fmaxf(sumsq * inv_n - mean * mean, 0.f);
  mean_b = rbf(mean);
  float sq; asm("sqrt.approx.f32 %0, %1;" : "=f"(sq) : "f"(rbf(rbf(var) + 1e-5f)));
  asm("rcp.approx.f32 %0, %1;" : "=f"(rsd) : "f"(rbf(sq)));
}
__device__ __forceinline__ void watch_flags(const unsigned* flags, int n, unsigned tag, uint32_t cnt_addr, int lane, long long tstart) {
  int done = 0;
  while (done < n) {
    unsigned v = (lane < n) ? ld_relaxed32(flags + lane * FS) : 0u;
    int c = __ffs(~__ballot_sync(0xffffffffu, v == tag)) - 1;
    if (c < 0) c = 32;
    if (timed_out(tstart)) c = n;
    if (c > done) { done = c; fence_acq(); __syncwarp(); if (lane == 0) sts_rel(cnt_addr, c); }
  }
}
__device__ __forceinline__ void wait_count(uint32_t cnt_addr, int it, int& have) {
  if (have > it) return;
  do { have = lds_acq(cnt_addr); } while (have <= it);
  fence_async_global();
}

template<int TA, int TB> __device__ __forceinline__ void wgmma_ss_n128(float (&d)[64], uint64_t da, uint64_t db, int scale_d) {
  asm volatile("{\n.reg .pred p;\nsetp.ne.b32 p, %66, 0;\n"
    "wgmma.mma_async.sync.aligned.m64n128k16.f32.bf16.bf16 {%0, %1, %2, %3, %4, %5, %6, %7, %8, %9, %10, %11, %12, %13, %14, %15, %16, %17, %18, %19, %20, %21, %22, %23, %24, %25, %26, %27, %28, %29, %30, %31, %32, %33, %34, %35, %36, %37, %38, %39, %40, %41, %42, %43, %44, %45, %46, %47, %48, %49, %50, %51, %52, %53, %54, %55, %56, %57, %58, %59, %60, %61, %62, %63}, %64, %65, p, 1, 1, %67, %68;\n}\n"
    : "+f"(d[0]), "+f"(d[1]), "+f"(d[2]), "+f"(d[3]), "+f"(d[4]), "+f"(d[5]), "+f"(d[6]), "+f"(d[7]), "+f"(d[8]), "+f"(d[9]), "+f"(d[10]), "+f"(d[11]), "+f"(d[12]), "+f"(d[13]), "+f"(d[14]), "+f"(d[15]), "+f"(d[16]), "+f"(d[17]), "+f"(d[18]), "+f"(d[19]), "+f"(d[20]), "+f"(d[21]), "+f"(d[22]), "+f"(d[23]), "+f"(d[24]), "+f"(d[25]), "+f"(d[26]), "+f"(d[27]), "+f"(d[28]), "+f"(d[29]), "+f"(d[30]), "+f"(d[31]), "+f"(d[32]), "+f"(d[33]), "+f"(d[34]), "+f"(d[35]), "+f"(d[36]), "+f"(d[37]), "+f"(d[38]), "+f"(d[39]), "+f"(d[40]), "+f"(d[41]), "+f"(d[42]), "+f"(d[43]), "+f"(d[44]), "+f"(d[45]), "+f"(d[46]), "+f"(d[47]), "+f"(d[48]), "+f"(d[49]), "+f"(d[50]), "+f"(d[51]), "+f"(d[52]), "+f"(d[53]), "+f"(d[54]), "+f"(d[55]), "+f"(d[56]), "+f"(d[57]), "+f"(d[58]), "+f"(d[59]), "+f"(d[60]), "+f"(d[61]), "+f"(d[62]), "+f"(d[63])
    : "l"(da), "l"(db), "r"(scale_d), "n"(TA), "n"(TB));
}
__device__ __forceinline__ void wgmma_rs_n32(float (&d)[16], const uint32_t (&a)[4], uint64_t db, int scale_d) {
  asm volatile("{\n.reg .pred p;\nsetp.ne.b32 p, %21, 0;\n"
    "wgmma.mma_async.sync.aligned.m64n32k16.f32.bf16.bf16 {%0, %1, %2, %3, %4, %5, %6, %7, %8, %9, %10, %11, %12, %13, %14, %15}, {%16, %17, %18, %19}, %20, p, 1, 1, 0;\n}\n"
    : "+f"(d[0]), "+f"(d[1]), "+f"(d[2]), "+f"(d[3]), "+f"(d[4]), "+f"(d[5]), "+f"(d[6]), "+f"(d[7]), "+f"(d[8]), "+f"(d[9]), "+f"(d[10]), "+f"(d[11]), "+f"(d[12]), "+f"(d[13]), "+f"(d[14]), "+f"(d[15])
    : "r"(a[0]), "r"(a[1]), "r"(a[2]), "r"(a[3]), "l"(db), "r"(scale_d));
}

struct Params {
  const bf16 *k, *v, *shift_k, *ssm_k, *ssm_D, *b_sp, *w_in, *pad;
  uint8_t role[136];
};

__device__ __forceinline__ void kv_tile(const Params& P, int tb, int j, int tid, uint32_t ks, uint32_t vs, uint32_t bar, uint32_t bar_read, uint32_t bar_store, long long tstart) {
  const int al = tid >> 3, dg = tid & 7;
  const int d0 = j * 64 + dg * 8;
  uint4 kr[11], vr[8], sk[4];
  #pragma unroll
  for (int r = 0; r < 4; r++) sk[r] = ldg_nc128(P.shift_k + (size_t)d0 * 4 + r * 8);
  #pragma unroll
  for (int r = 0; r < 3; r++) kr[r] = (al == 0 && tb > 0) ? ldg_nc128(P.k + (size_t)(tb * 128 - 3 + r) * 448 + d0) : make_uint4(0, 0, 0, 0);
  mbar_wait(bar, 0, tstart);
  #pragma unroll
  for (int r = 0; r < 11; r++) if (r >= 3 || al > 0) kr[r] = lds128(ks + (al * 8 - 3 + r) * 128 + dg * 16);
  #pragma unroll
  for (int r = 0; r < 8; r++) vr[r] = lds128(vs + (al * 8 + r) * 128 + dg * 16);
  uint32_t tp[4][4];
  #pragma unroll
  for (int r = 0; r < 4; r++) {
    tp[0][r] = __byte_perm(sk[r].x, sk[r].z, 0x5410); tp[1][r] = __byte_perm(sk[r].x, sk[r].z, 0x7632);
    tp[2][r] = __byte_perm(sk[r].y, sk[r].w, 0x5410); tp[3][r] = __byte_perm(sk[r].y, sk[r].w, 0x7632);
  }
  uint32_t kv[8][4];
  #pragma unroll
  for (int r = 0; r < 8; r++) {
    const uint32_t* k3 = reinterpret_cast<const uint32_t*>(&kr[r]);
    const uint32_t* k2 = reinterpret_cast<const uint32_t*>(&kr[r + 1]);
    const uint32_t* k1 = reinterpret_cast<const uint32_t*>(&kr[r + 2]);
    const uint32_t* k0 = reinterpret_cast<const uint32_t*>(&kr[r + 3]);
    const uint32_t* vv = reinterpret_cast<const uint32_t*>(&vr[r]);
    #pragma unroll
    for (int c = 0; c < 4; c++) {
      uint32_t a = bmul2(k3[c], tp[3][c]);
      a = badd2(a, bmul2(k2[c], tp[2][c]));
      a = badd2(a, bmul2(k1[c], tp[1][c]));
      a = badd2(a, bmul2(k0[c], tp[0][c]));
      kv[r][c] = bmul2(a, vv[c]);
    }
  }
  mbar_arrive(bar_read);
  mbar_wait(bar_store, 0, tstart);
  #pragma unroll
  for (int dd = 0; dd < 8; dd++) {
    uint32_t sel = (dd & 1) ? 0x7632 : 0x5410;
    uint4 o;
    o.x = __byte_perm(kv[7][dd >> 1], kv[6][dd >> 1], sel); o.y = __byte_perm(kv[5][dd >> 1], kv[4][dd >> 1], sel);
    o.z = __byte_perm(kv[3][dd >> 1], kv[2][dd >> 1], sel); o.w = __byte_perm(kv[1][dd >> 1], kv[0][dd >> 1], sel);
    g_kvimg[(size_t)(d0 + dd) * 256 + tb * 16 + al] = o;
  }
}

constexpr uint32_t SLOT = 16384;
constexpr uint32_t OFF_W = 0, OFF_X = 7 * SLOT, OFF_MISC = 14 * SLOT;
constexpr uint32_t OFF_XS = OFF_MISC;
constexpr uint32_t OFF_W1 = OFF_MISC + 1024;
constexpr uint32_t OFF_BAR = OFF_MISC + 2048;
constexpr uint32_t B_FULL = OFF_BAR, B_EMPTY = B_FULL + 56, B_WFULL = B_EMPTY + 56, B_UFULL = B_WFULL + 56, B_UEMPTY = B_UFULL + 112,
                   B_XE = B_UEMPTY + 64, B_W1 = B_XE + 8, B_Y = B_W1 + 8, B_KV = B_Y + 8, B_SFULL = B_KV + 8, B_SDONE = B_SFULL + 8, B_W1B = B_SDONE + 8, B_TAG = B_W1B + 8, B_KVT = B_TAG + 8, B_X6 = B_KVT + 8,
                   B_ZST = B_X6 + 8, B_UPUB = B_ZST + 16, B_UST = B_UPUB + 8, B_KVRD = B_X6, B_ZOUT = B_UST + 8;
constexpr int G2S = 6;
constexpr uint32_t OFF_SW = OFF_W + 6 * SLOT;
constexpr uint32_t OFF_TAG = OFF_BAR + 648, OFF_CNT = OFF_BAR + 656;
constexpr uint32_t OFF_TS = OFF_BAR + 672;
constexpr int CST = 4;
constexpr uint32_t C_H0 = 16;
constexpr uint32_t C_H1 = C_H0 + 4096 + 16;
constexpr uint32_t C_KVB = ((C_H1 + 4096 + 16 + 127) / 128) * 128 + 768;
constexpr uint32_t C_KVA = C_KVB + 4096 + 128 + 768;
constexpr uint32_t C_SLOT = C_KVA + 4096;
constexpr uint32_t C_ZERO_END = CST * C_SLOT;
constexpr uint32_t C_KT = 73728, C_KT_SZ = 136 * 128 + 128 * 128 + 512;
static_assert(C_ZERO_END <= C_KT, "conv smem map");
constexpr uint32_t CB_HFULL = OFF_BAR + 464, CB_KVFULL = CB_HFULL + 32, CB_READY = CB_KVFULL + 32, CB_EMPTY = CB_READY + 32, CB_ZERO = CB_EMPTY + 32,
                   CB_KT = CB_ZERO + 8, CB_KTE = CB_KT + 16, CB_KPUB = CB_KTE + 8;

__global__ void __launch_bounds__(512, 1)
fused_kernel(const __grid_constant__ Params P, const __grid_constant__ CUtensorMap tmX, const __grid_constant__ CUtensorMap tmWin,
             const __grid_constant__ CUtensorMap tmWs, const __grid_constant__ CUtensorMap tmK, const __grid_constant__ CUtensorMap tmV,
             const __grid_constant__ CUtensorMap tmK2, const __grid_constant__ CUtensorMap tmWsp, const __grid_constant__ CUtensorMap tmWout, const __grid_constant__ CUtensorMap tmOut) {
  extern __shared__ __align__(1024) uint8_t smem_raw[];
  const uint32_t sb = smem_u32(smem_raw);
  const long long tstart = clock64();
  const int bid = blockIdx.x;
  if (threadIdx.x == 0) TG(40);
  unsigned ep = 0;
  if (threadIdx.x == 480) ep = ld_relaxed32(g_epoch + bid);
  const int wg = __shfl_sync(0xffffffffu, threadIdx.x >> 7, 0), w = __shfl_sync(0xffffffffu, (threadIdx.x >> 5) & 3, 0);
#define THREAD_IDS const uint32_t tx = __shfl_sync(0xffffffffu, threadIdx.x, threadIdx.x & 31); \
                   const int tid = tx & 127, lane = tx & 31, g = lane >> 2, q = lane & 3; (void)tid; (void)g; (void)q;
  if (threadIdx.x == 0) {
    #pragma unroll
    for (int i = 0; i < 7; i++) { mbar_init(sb + B_FULL + 8 * i, 1); mbar_init(sb + B_UFULL + 8 * i, 1); }
    mbar_init(sb + B_SFULL, 1); mbar_init(sb + CB_KT, 1); mbar_init(sb + CB_KT + 8, 1);
    fence_async_smem();
  } else if (threadIdx.x == 128) {
    sts128(sb + OFF_CNT, make_uint4(0, 0, 0, 0));
    prefetch_tmap(&tmWs); prefetch_tmap(&tmX); prefetch_tmap(&tmWin); prefetch_tmap(&tmK); prefetch_tmap(&tmV);
  } else if (threadIdx.x == 256) {
    #pragma unroll
    for (int i = 0; i < 7; i++) { mbar_init(sb + B_EMPTY + 8 * i, 2); mbar_init(sb + B_WFULL + 8 * i, 1); }
    mbar_init(sb + B_XE, 1); mbar_init(sb + B_W1, 3); mbar_init(sb + B_W1B, 2);
    fence_async_smem();
  } else if (threadIdx.x == 288) {
    #pragma unroll
    for (int i = 7; i < 12; i++) mbar_init(sb + B_UFULL + 8 * i, 1);
    mbar_init(sb + B_ZST, 128); mbar_init(sb + B_ZST + 8, 128); mbar_init(sb + B_UPUB, 256); mbar_init(sb + B_UST, 256); mbar_init(sb + B_KVRD, 128); mbar_init(sb + B_ZOUT, 2);
    fence_async_smem();
  } else if (threadIdx.x == 320) {
    #pragma unroll
    for (int i = 0; i < 8; i++) mbar_init(sb + B_UEMPTY + 8 * i, 1);
    mbar_init(sb + B_Y, 1); mbar_init(sb + B_KV, 1); mbar_init(sb + B_SDONE, 1); mbar_init(sb + B_TAG, 1); mbar_init(sb + B_KVT, 1);
    mbar_init(sb + CB_KTE, 1); mbar_init(sb + CB_KPUB, 256); mbar_init(sb + CB_KPUB + 8, 256);
    fence_async_smem();
  } else if (threadIdx.x == 384) {
    #pragma unroll
    for (int i = 0; i < 4 * CST + 1; i++) mbar_init(sb + CB_HFULL + 8 * i, (i >= 2 * CST && i < 3 * CST) ? 4 : (i == 4 * CST ? 128 : 1));
    fence_async_smem();
  }
  const int role = P.role[bid];
  const bool is_gemm = role < 128;
  const int tb = role >> 3, j = role & 7, cidx = role & 127;
  if (threadIdx.x < 32) {
    __syncwarp();
    bar_arrive(0, 512);
    if (threadIdx.x == 0) {
      TS(20);
      if (is_gemm) {
        mbar_expect_tx(sb + B_SFULL, 56 * 128);
        tma_load_2d(sb + OFF_SW, &tmWs, sb + B_SFULL, 896 + 128 * j + (tb & 1) * 64, (tb >> 1) * 56);
        #pragma unroll 1
        for (int c = 0; c < 6; c++) {
          #pragma unroll 1
          for (int xc = max(2 * c - 1, 0); xc <= min(2 * c, 6); xc++) {
            mbar_expect_tx(sb + B_UFULL + 8 * xc, SLOT);
            tma_load_2d(sb + OFF_X + xc * SLOT, &tmX, sb + B_UFULL + 8 * xc, xc * 64, tb * 128);
          }
          mbar_expect_tx(sb + B_FULL + 8 * c, SLOT);
          tma_load_3d(sb + OFF_W + c * SLOT, &tmWin, sb + B_FULL + 8 * c, 0, c * 64, 14 + 2 * j);
        }
      } else if (cidx < 16) {
        mbar_expect_tx(sb + CB_KT, C_KT_SZ);
        tma_load_2d(sb + C_KT, &tmK, sb + CB_KT, 0, cidx * 128 - 8);
        tma_load_2d(sb + C_KT + 136 * 128, &tmV, sb + CB_KT, 0, cidx * 128);
        bulk_load(sb + C_KT + 264 * 128, P.shift_k, 512, sb + CB_KT);
      }
      if (is_gemm && tb < 7) tma_prefetch_3d(&tmWin, 0, tb * 64, 2 * j);
      TS(19);
    }
    __syncwarp();
  } else {
    bar_sync(0, 512);
  }
  if (threadIdx.x == 256) TS(0);
  if (threadIdx.x == 480) { sts32f(sb + OFF_TAG, __uint_as_float(ep + 1)); mbar_arrive(sb + B_TAG); }
  __syncwarp();
#define GET_TAG() (mbar_wait(sb + B_TAG, 0, tstart), lds32(sb + OFF_TAG))

  if (!is_gemm) {
    const int nch = (448 - cidx + NCONV - 1) / NCONV;
    if (wg < 2) {
      asm volatile("setmaxnreg.inc.sync.aligned.u32 224;");
      THREAD_IDS
      if (wg == 0) bar_sync(4, 128);
      if (cidx < 16) {
        const int al = tx >> 4, dq = tx & 15;
        #pragma unroll 1
        for (int pass = 0; pass < 4; pass++) {
          const int jb = max(pass - 1, 0), h = jb;
          if (pass) { if (tx == 0 && pass < 3) TS(43 + pass); mbar_wait(sb + CB_KT + 8 * h, 0, tstart); }
          const uint32_t ks = sb + C_KT + h * C_KT_SZ + (al * 8 + 5) * 128 + dq * 8, vs = sb + C_KT + h * C_KT_SZ + (136 + al * 8) * 128 + dq * 8;
          uint2 kr[11], vr[8];
          #pragma unroll
          for (int r = 0; r < 11; r++) kr[r] = lds64(ks + r * 128);
          #pragma unroll
          for (int r = 0; r < 8; r++) vr[r] = lds64(vs + r * 128);
          const uint4 s0 = lds128(sb + C_KT + h * C_KT_SZ + 264 * 128 + dq * 32), s1 = lds128(sb + C_KT + h * C_KT_SZ + 264 * 128 + dq * 32 + 16);
          const uint32_t t00 = __byte_perm(s0.x, s0.z, 0x5410), t10 = __byte_perm(s0.x, s0.z, 0x7632), t20 = __byte_perm(s0.y, s0.w, 0x5410), t30 = __byte_perm(s0.y, s0.w, 0x7632);
          const uint32_t t01 = __byte_perm(s1.x, s1.z, 0x5410), t11 = __byte_perm(s1.x, s1.z, 0x7632), t21 = __byte_perm(s1.y, s1.w, 0x5410), t31 = __byte_perm(s1.y, s1.w, 0x7632);
          uint32_t kv[8][2];
          #pragma unroll
          for (int r = 0; r < 8; r++) {
            kv[r][0] = bmul2(badd2(badd2(badd2(bmul2(kr[r].x, t30), bmul2(kr[r + 1].x, t20)), bmul2(kr[r + 2].x, t10)), bmul2(kr[r + 3].x, t00)), vr[r].x);
            kv[r][1] = bmul2(badd2(badd2(badd2(bmul2(kr[r].y, t31), bmul2(kr[r + 1].y, t21)), bmul2(kr[r + 2].y, t11)), bmul2(kr[r + 3].y, t01)), vr[r].y);
          }
          #pragma unroll
          for (int dd = 0; dd < 4; dd++) {
            const uint32_t sel = (dd & 1) ? 0x7632 : 0x5410;
            uint4 o;
            o.x = __byte_perm(kv[7][dd >> 1], kv[6][dd >> 1], sel); o.y = __byte_perm(kv[5][dd >> 1], kv[4][dd >> 1], sel);
            o.z = __byte_perm(kv[3][dd >> 1], kv[2][dd >> 1], sel); o.w = __byte_perm(kv[1][dd >> 1], kv[0][dd >> 1], sel);
            if (pass) g_kvimg[(size_t)(jb * 64 + dq * 4 + dd) * 256 + cidx * 16 + al] = o;
          }
          if (pass == 1) {
            bar_sync(3, 256);
            if (tx == 0) TS(46);
            if (tx == 96) { const unsigned tg = GET_TAG(); fence_async_global(); st_release(g_kvflag + cidx * FS, tg); TS(40); }
            __syncwarp();
            bar_sync(3, 256);
          } else if (pass) { mbar_arrive(sb + CB_KPUB + 8 * (pass - 2)); if (tx == 0) TS(47); }
        }
      }
      const unsigned tag = GET_TAG();
      float acc[8][16];
      uint32_t a[16][4];
      const int g0 = g & 1, gam = g >> 1;
      const int rho = 2 * w + g0 + 16 * gam;
      const uint32_t aoff = g0 ? (C_H0 + 2 * (rho + 2 * q - 7)) : (C_H1 + 2 * (rho + 2 * q - 6));
      const bool c1 = gam >= 2 && q >= 2, c2 = gam >= 2 && q < 2;
      const bool isB = gam & 1, sp2 = gam == 3 && q == 1, nb2 = isB && !sp2;
      const int u1 = q + gam + (c2 ? 4 : 0), off = u1 + (nb2 ? 8 : 0), res = u1 & 7;
      const int pg = isB ? (res < 4 ? 0 : 2) : ((res >= 1 && res <= 4) ? 1 : 3);
      const int pq = isB ? (res < 4 ? res : (res < 6 ? res - 2 : res - 6)) : ((res >= 1 && res <= 4) ? res - 1 : (res == 0 ? 1 : (res == 7 ? 0 : res - 3)));
      const int src2 = (pg * 2 + g0) * 4 + pq;
      const int yoff = ((off >> 2) * 8 + g0 * 4 + w) * 4 + (off & 3);
      constexpr uint64_t HI_KV = desc_hi(C_KVA - C_KVB, 128, 0);
      if (wg == 1) bar_arrive(1, 256);
      int s = wg; uint32_t ph = 0;
      #pragma unroll 1
      for (int i = wg; i < nch; i += 2) {
        const int ch = cidx + i * NCONV;
        const uint32_t sl = sb + s * C_SLOT;
        mbar_wait(sb + CB_READY + 8 * s, ph, tstart);
        #pragma unroll
        for (int m = 0; m < 16; m++) {
          a[m][0] = lds32(sl + aoff + m * 256 + 16); a[m][1] = lds32(sl + aoff + m * 256 + 16 + 128);
          a[m][2] = lds32(sl + aoff + m * 256);      a[m][3] = lds32(sl + aoff + m * 256 + 128);
        }
        mbar_wait(sb + CB_KVFULL + 8 * s, ph, tstart);
        const uint64_t db = mkdesc(sl + C_KVB, HI_KV);
        bar_sync(1 + wg, 256);
        wgmma_fence();
        #pragma unroll
        for (int m = 0; m < 16; m++) {
          #pragma unroll
          for (int b = 7; b >= 0; b--)
            if (32 * b + 32 > 16 * m) wgmma_rs_n32(acc[b], a[m], db + (uint64_t)(int64_t)(32 * b - 16 * m), m > 0);
        }
        wgmma_commit();
        if (i + 1 < nch) bar_arrive(1 + (wg ^ 1), 256);
        wgmma_wait<0>();
        if (tid == 0) mbar_arrive(sb + CB_EMPTY + 8 * s);
        #define ACC(J, r) acc[(J) >> 2][4 * ((J) & 3) + (r)]
        float V[32][2], W[16][2];
        #pragma unroll
        for (int J = 0; J < 32; J++) { V[J][0] = ACC(J, 0) + (J > 0 ? ACC(J - 1, 2) : 0.f); V[J][1] = ACC(J, 1) + (J > 0 ? ACC(J - 1, 3) : 0.f); }
        #undef ACC
        #pragma unroll
        for (int k = 0; k < 16; k++)
          #pragma unroll
          for (int p = 0; p < 2; p++) {
            float prev = k > 0 ? V[2 * k - 1][p] : 0.f;
            float snd = c1 ? prev : (c2 ? V[2 * k][p] : V[2 * k + 1][p]);
            float keep = c2 ? V[2 * k + 1][p] : V[2 * k][p];
            W[k][p] = keep + __shfl_xor_sync(0xffffffffu, snd, 18);
          }
        uint32_t* yp = reinterpret_cast<uint32_t*>(g_yimg) + (size_t)ch * 1024 + yoff;
        #pragma unroll
        for (int k = 0; k < 8; k++) {
          float r[2];
          #pragma unroll
          for (int p = 0; p < 2; p++) {
            float prev = k > 0 ? W[2 * k - 1][p] : 0.f;
            float snd = sp2 ? prev : (nb2 ? W[2 * k][p] : W[2 * k + 1][p]);
            float keep = nb2 ? W[2 * k + 1][p] : W[2 * k][p];
            r[p] = keep + __shfl_sync(0xffffffffu, snd, src2);
          }
          yp[k * 128] = pack_bf16(r[0], r[1]);
        }
        if (tid == 0 && i < 24) TS(2 + i);
        s += 2; if (s >= CST) { s -= CST; ph ^= 1; }
      }
      bar_sync(4 + wg, 128);
      if (tid == 0) { st_release(g_cflag + (cidx * 2 + wg) * FS, tag); if (wg == 0) g_epoch[bid] = tag; TS(30 + wg); if (((nch - 1) & 1) == wg) TDUMP(); }
    } else if (wg == 2) {
      asm volatile("setmaxnreg.dec.sync.aligned.u32 24;");
      THREAD_IDS
      if (w == 0) {
        if (lane == 0) {
          if (cidx < 16) {
            mbar_wait(sb + CB_KT, 0, tstart);
            #pragma unroll 1
            for (int h = 1; h < 3; h++) {
              mbar_expect_tx(sb + CB_KT + 8 * h, C_KT_SZ);
              tma_load_2d(sb + C_KT + h * C_KT_SZ, &tmK, sb + CB_KT + 8 * h, 64 * h, cidx * 128 - 8);
              tma_load_2d(sb + C_KT + h * C_KT_SZ + 136 * 128, &tmV, sb + CB_KT + 8 * h, 64 * h, cidx * 128);
              bulk_load(sb + C_KT + h * C_KT_SZ + 264 * 128, P.shift_k + 256 * h, 512, sb + CB_KT + 8 * h);
            }
          }
          mbar_wait(sb + CB_ZERO, 0, tstart);
          #pragma unroll 1
          for (int i = 0; i < CST; i++) {
            mbar_expect_tx(sb + CB_HFULL + 8 * i, 4096);
            bulk_load(sb + i * C_SLOT + C_H0, P.ssm_k + (size_t)(cidx + i * NCONV) * 2048, 4096, sb + CB_HFULL + 8 * i);
          }
          int s = 0, have = 0; uint32_t ph = 0;
          #pragma unroll 1
          for (int i = 0; i < nch; i++) {
            const int ch = cidx + i * NCONV;
            const uint32_t sl = sb + s * C_SLOT;
            if (i >= CST) {
              mbar_wait(sb + CB_EMPTY + 8 * s, ph ^ 1, tstart);
              mbar_expect_tx(sb + CB_HFULL + 8 * s, 4096);
              bulk_load(sl + C_H0, P.ssm_k + (size_t)ch * 2048, 4096, sb + CB_HFULL + 8 * s);
            }
            wait_count(sb + OFF_CNT + 8, ch >> 6, have);
            if (i == 0) TS(1);
            mbar_expect_tx(sb + CB_KVFULL + 8 * s, 8192);
            bulk_load(sl + C_KVA, g_kvimg + (size_t)ch * 256, 4096, sb + CB_KVFULL + 8 * s);
            bulk_load(sl + C_KVB + 16, g_kvimg + (size_t)ch * 256, 4096, sb + CB_KVFULL + 8 * s);
            if (++s == CST) { s = 0; ph ^= 1; }
          }
        }
      } else if (w == 1) {
        const unsigned tag = GET_TAG();
        #pragma unroll 1
        for (int jj = 0; jj < 7; jj++) {
          while (true) {
            unsigned v = (lane < 16) ? ld_relaxed32(g_kvflag + (jj * 16 + lane) * FS) : tag;
            if (__all_sync(0xffffffffu, v == tag) || timed_out(tstart)) break;
          }
          fence_acq(); __syncwarp();
          if (lane == 0) sts_rel(sb + OFF_CNT + 8, jj + 1);
        }
      } else if (tid == 64 && cidx < 16) {
        const unsigned tag = GET_TAG();
        #pragma unroll 1
        for (int h = 0; h < 2; h++) {
          mbar_wait(sb + CB_KPUB + 8 * h, 0, tstart);
          fence_async_global();
          st_release(g_kvflag + (16 + 16 * h + cidx) * FS, tag);
          TS(41 + h);
        }
      }
    } else {
      asm volatile("setmaxnreg.dec.sync.aligned.u32 40;");
      THREAD_IDS
      #pragma unroll 4
      for (uint32_t i = tid * 16; i < C_ZERO_END; i += 128 * 16) sts128(sb + i, make_uint4(0, 0, 0, 0));
      fence_async_smem();
      mbar_arrive(sb + CB_ZERO);
      int s = 0; uint32_t ph = 0;
      #pragma unroll 1
      for (int i = 0; i < nch; i++) {
        const uint32_t sl = sb + s * C_SLOT;
        mbar_wait(sb + CB_HFULL + 8 * s, ph, tstart);
        #pragma unroll
        for (int r = 0; r < 2; r++) {
          const int c = tid + r * 128;
          uint4 v = lds128(sl + C_H0 + c * 16); uint32_t pv = lds32(sl + C_H0 + c * 16 - 4);
          uint4 o; o.x = __byte_perm(pv, v.x, 0x5432); o.y = __byte_perm(v.x, v.y, 0x5432); o.z = __byte_perm(v.y, v.z, 0x5432); o.w = __byte_perm(v.z, v.w, 0x5432);
          sts128(sl + C_H1 + c * 16, o);
        }
        __syncwarp();
        if (lane == 0) mbar_arrive(sb + CB_READY + 8 * s);
        if (++s == CST) { s = 0; ph ^= 1; }
      }
    }
  } else {
    if (wg < 2) {
      asm volatile("setmaxnreg.inc.sync.aligned.u32 184;");
      THREAD_IDS
      if (wg == 0) bar_sync(1, 128);
      constexpr uint64_t HI_SW_K = desc_hi(16, 1024, 1);
      constexpr uint64_t HI_SW_MN = desc_hi(8192, 1024, 1);
      constexpr uint64_t HI_Z2 = desc_hi(2048, 128, 0);
      constexpr uint64_t HI_U = desc_hi(128, 1024, 0);
      const bool lead = (tid == 0);
      float acc2[64], acc1[64];
      const int row0 = wg * 64 + w * 16 + g;
      const uint64_t dX = mkdesc(sb + OFF_X + wg * 8192, HI_SW_K), dW = mkdesc(sb + OFF_W, HI_SW_MN);
      auto g1_chunk = [&](float (&acc)[64], int c, uint32_t z1, bool first) {
        mbar_wait(sb + (z1 ? B_WFULL : B_FULL) + 8 * c, 0, tstart);
        wgmma_fence();
        #pragma unroll
        for (int k = 0; k < 4; k++) wgmma_ss_n128<0, 1>(acc, dX + (c * 1024 + k * 2), dW + (c * 1024 + k * 128), !(first && k == 0));
        wgmma_commit();
      };
      auto release = [&](int c) { if (lead) mbar_arrive(sb + B_EMPTY + 8 * c); };
      #pragma unroll 1
      for (int c = 0; c < 7; c++) {
        mbar_wait(sb + B_UFULL + 8 * c, 0, tstart);
        g1_chunk(acc2, c, 0, c == 0);
        if (tx == 0) TS(c == 0 ? 1 : 32 + c);
        if (c > 0) { wgmma_wait<1>(); release(c - 1); }
      }
      float2 w1[16];
      mbar_wait(sb + B_W1, 0, tstart);
      const unsigned tag = lds32(sb + OFF_TAG);
      #pragma unroll
      for (int J = 0; J < 16; J++) w1[J] = lds64f(sb + OFF_W1 + (128 + J * 8 + 2 * q) * 4);
      const float2 xs0 = lds64f(sb + OFF_XS + row0 * 8), xs1 = lds64f(sb + OFF_XS + (row0 + 8) * 8);
      g1_chunk(acc1, 0, 1, true);
      wgmma_wait<1>();
      release(6);
      if (lead) TS(wg ? 60 : 2);
      const float ka0 = 0.7978845608028654f * xs0.y, kb0 = 0.035677408136300125f * xs0.y * xs0.y * xs0.y, hr0 = 0.5f * xs0.y, nm0 = -xs0.x;
      const float ka1 = 0.7978845608028654f * xs1.y, kb1 = 0.035677408136300125f * xs1.y * xs1.y * xs1.y, hr1 = 0.5f * xs1.y, nm1 = -xs1.x;
      float s0 = 0.f, q0 = 0.f, s1 = 0.f, q1 = 0.f;
      auto z2_part = [&](int J0) {
        #pragma unroll
        for (int J = J0; J < J0 + 8; J++) {
          float a = gelu_s(fmaf(nm0, w1[J].x, acc2[4 * J]), ka0, kb0, hr0), b = gelu_s(fmaf(nm0, w1[J].y, acc2[4 * J + 1]), ka0, kb0, hr0);
          float c = gelu_s(fmaf(nm1, w1[J].x, acc2[4 * J + 2]), ka1, kb1, hr1), d = gelu_s(fmaf(nm1, w1[J].y, acc2[4 * J + 3]), ka1, kb1, hr1);
          acc2[4 * J] = a; acc2[4 * J + 1] = b; acc2[4 * J + 2] = c; acc2[4 * J + 3] = d;
          s0 += a; s0 += b; q0 = fmaf(a, a, q0); q0 = fmaf(b, b, q0); s1 += c; s1 += d; q1 = fmaf(c, c, q1); q1 = fmaf(d, d, q1);
        }
      };
      const uint32_t t6 = tag & 63u;
      z2_part(0);
      g1_chunk(acc1, 1, 1, false);
      z2_part(8);
      #pragma unroll
      for (int o = 1; o < 4; o <<= 1) {
        s0 += __shfl_xor_sync(0xffffffffu, s0, o); q0 += __shfl_xor_sync(0xffffffffu, q0, o);
        s1 += __shfl_xor_sync(0xffffffffu, s1, o); q1 += __shfl_xor_sync(0xffffffffu, q1, o);
      }
      if (q < 2) st_relaxed64(g_zstat + (tb * 7 + j) * 128 + row0 + q * 8, make_uint2(tag_enc(q ? s1 : s0, t6), tag_enc(q ? q1 : q0, t6)));
      if (lead) TS(wg ? 61 : 3);
      g1_chunk(acc1, 2, 1, false);
      wgmma_wait<1>();
      release(0); release(1);
      {
        const uint2* zs = g_zstat + (tb * 7 + q) * 128 + row0;
        uint2 a, b, c = make_uint2(t6, t6), d = c;
        while (true) {
          a = ld_relaxed64(zs); b = ld_relaxed64(zs + 8);
          if (q < 3) { c = ld_relaxed64(zs + 512); d = ld_relaxed64(zs + 520); }
          if (__all_sync(0xffffffffu, tag_ok4(make_uint4(a.x, a.y, b.x, b.y), t6) && tag_ok4(make_uint4(c.x, c.y, d.x, d.y), t6)) || timed_out(tstart)) break;
        }
        float ts0 = tag_val(a.x) + tag_val(c.x), tq0 = tag_val(a.y) + tag_val(c.y), ts1 = tag_val(b.x) + tag_val(d.x), tq1 = tag_val(b.y) + tag_val(d.y);
        #pragma unroll
        for (int o = 1; o < 4; o <<= 1) {
          ts0 += __shfl_xor_sync(0xffffffffu, ts0, o); tq0 += __shfl_xor_sync(0xffffffffu, tq0, o);
          ts1 += __shfl_xor_sync(0xffffffffu, ts1, o); tq1 += __shfl_xor_sync(0xffffffffu, tq1, o);
        }
        if (lead) TS(wg ? 62 : 4);
        float m0, r0, m1, r1;
        ln_scalars(ts0, tq0, 1.0f / 896.0f, m0, r0); ln_scalars(ts1, tq1, 1.0f / 896.0f, m1, r1);
        m0 = -m0 * r0; m1 = -m1 * r1;
        uint32_t* zo = reinterpret_cast<uint32_t*>(g_z2img + (size_t)(j * 32 + 2 * tb + wg) * 1024) + (2 * w) * 16 * 32 + lane;
        #pragma unroll
        for (int J = 0; J < 16; J++) {
          zo[J * 32] = pack_bf16(fmaf(acc2[4 * J], r0, m0), fmaf(acc2[4 * J + 1], r0, m0));
          zo[(16 + J) * 32] = pack_bf16(fmaf(acc2[4 * J + 2], r1, m1), fmaf(acc2[4 * J + 3], r1, m1));
        }
      }
      mbar_arrive(sb + B_ZST + 8 * wg);
      if (tx == 0) TS(15);
      #pragma unroll 1
      for (int c = 3; c < 7; c++) {
        g1_chunk(acc1, c, 1, false);
        wgmma_wait<1>();
        release(c - 1);
      }
      mbar_wait(sb + B_W1B, 0, tstart);
      #pragma unroll
      for (int J = 0; J < 8; J++) w1[J] = lds64f(sb + OFF_W1 + (J * 8 + 2 * q) * 4);
      const uint32_t bb0 = (uint32_t)__bfloat16_as_ushort(P.b_sp[tb * 128 + row0]) * 0x10001u, bb1 = (uint32_t)__bfloat16_as_ushort(P.b_sp[tb * 128 + row0 + 8]) * 0x10001u;
      wgmma_wait<0>();
      release(6);
      if (lead) TS(wg ? 59 : 16);
      uint32_t z1p[32];
      #pragma unroll
      for (int J = 0; J < 16; J++) {
        if (J < 8) w1[J + 8] = lds64f(sb + OFF_W1 + ((J + 8) * 8 + 2 * q) * 4);
        z1p[2 * J] = pack_bf16(gelu_s(fmaf(nm0, w1[J].x, acc1[4 * J]), ka0, kb0, hr0), gelu_s(fmaf(nm0, w1[J].y, acc1[4 * J + 1]), ka0, kb0, hr0));
        z1p[2 * J + 1] = pack_bf16(gelu_s(fmaf(nm1, w1[J].x, acc1[4 * J + 2]), ka1, kb1, hr1), gelu_s(fmaf(nm1, w1[J].y, acc1[4 * J + 3]), ka1, kb1, hr1));
      }
      if (lead) TS(wg ? 51 : 6);
      {
        int s = 0, sp = 0; uint32_t par = 1;
        const uint64_t dA = mkdesc(sb + OFF_W + wg * 8192, HI_SW_K), dB = mkdesc(sb + OFF_X, HI_Z2);
        #pragma unroll 1
        for (int it = 0; it < 32; it++) {
          mbar_wait(sb + B_FULL + 8 * s, par, tstart);
          if (it == 0 && tx == 0) TS(7);
          if ((it & 7) == 7 && tx == 0) TS(29 + (it >> 3));
          if (tx == 0 && (it == 18 || it == 19)) TS(54 + 3 * (it - 18));
          if (tx == 128 && it == 18) TS(58);
          wgmma_fence();
          #pragma unroll
          for (int k = 0; k < 4; k++) wgmma_ss_n128<0, 1>(acc2, dA + (s * 1024 + k * 2), dB + (s * 1024 + k * 256), (it | k) != 0);
          wgmma_commit();
          if (it > 0) { wgmma_wait<1>(); if (lead) mbar_arrive(sb + B_EMPTY + 8 * sp); if (++sp == G2S) sp = 0; }
          if (++s == G2S) { s = 0; par ^= 1; }
        }
        wgmma_wait<0>();
        if (lead) mbar_arrive(sb + B_EMPTY + 8 * sp);
      }
      if (lead) TS(wg ? 23 : 8);
      {
        uint32_t* ug = reinterpret_cast<uint32_t*>(g_uimg + (size_t)(tb * 14 + 2 * j) * 1024) + (8 * wg + 2 * w) * 256 + lane;
        #pragma unroll
        for (int J = 0; J < 16; J++) {
          z1p[2 * J] = bmul2(z1p[2 * J], badd2(pack_bf16(acc2[4 * J], acc2[4 * J + 1]), bb0));
          z1p[2 * J + 1] = bmul2(z1p[2 * J + 1], badd2(pack_bf16(acc2[4 * J + 2], acc2[4 * J + 3]), bb1));
          ug[(J >> 3) * 4096 + (J & 7) * 32] = z1p[2 * J];
          ug[(J >> 3) * 4096 + (8 + (J & 7)) * 32] = z1p[2 * J + 1];
        }
        mbar_arrive(sb + B_UPUB);
        if (tx == 0) TS(17);
        bar_sync(3, 256);
        const uint32_t uo = sb + OFF_X + (8 * wg + 2 * w) * 1024 + lane * 4;
        #pragma unroll
        for (int J = 0; J < 16; J++) {
          sts32(uo + (J >> 3) * SLOT + (J & 7) * 128, z1p[2 * J]);
          sts32(uo + (J >> 3) * SLOT + (8 + (J & 7)) * 128, z1p[2 * J + 1]);
        }
      }
      fence_async_smem();
      mbar_arrive(sb + B_UST);
      const int drow = j * 64 + w * 16 + g;
      uint32_t kvw[2][8];
      mbar_wait(sb + B_KV, 0, tstart);
      #pragma unroll
      for (int h = 0; h < 2; h++) {
        const uint32_t* kp = reinterpret_cast<const uint32_t*>(g_kvimg + (size_t)(drow + 8 * h) * 256 + tb * 16 + wg * 8) + (3 - q);
        #pragma unroll
        for (int J = 0; J < 8; J++) kvw[h][J] = ldg_cg32(kp + J * 4);
      }
      const uint32_t dd0 = (uint32_t)__bfloat16_as_ushort(P.ssm_D[drow]) * 0x10001u, dd1 = (uint32_t)__bfloat16_as_ushort(P.ssm_D[drow + 8]) * 0x10001u;
      {
        const uint64_t dA = mkdesc(sb + OFF_W + wg * 8192, HI_SW_MN), dB = mkdesc(sb + OFF_X, HI_U);
        int us = wg;
        #pragma unroll 1
        for (int n = 0; n < 7; n++) {
          const int jj = (n == 0) ? j : (n - 1 + (n > j));
          mbar_wait(sb + B_WFULL + 8 * jj, 1, tstart);
          mbar_wait(sb + (n == 0 ? B_UST : B_UFULL + 8 * (2 * n - 2 + wg)), (n > 0 && 2 * n - 2 + wg < 7) ? 1 : 0, tstart);
          if (n == 1 && tx == 0) TS(10);
          wgmma_fence();
          #pragma unroll
          for (int k = 0; k < 4; k++) wgmma_ss_n128<1, 0>(acc1, dA + (jj * 1024 + k * 128), dB + (us * 1024 + k * 16), (n | k) != 0);
          wgmma_commit();
          if (n >= 1 && n <= 4) { wgmma_wait<1>(); if (lead) mbar_arrive(sb + B_UEMPTY + 8 * (2 * n - 2 + wg)); }
          us += 2; if (us >= 6) us -= 6;
        }
      }
      if (tx == 0) TS(18);
      mbar_wait(sb + B_Y, 0, tstart);
      uint4 yv[2][2];
      #pragma unroll
      for (int h = 0; h < 2; h++)
        #pragma unroll
        for (int p = 0; p < 2; p++) yv[h][p] = ldg_cg128(g_yimg + (size_t)(drow + 8 * h) * 256 + (2 * tb + wg) * 8 + p * 4 + q);
      wgmma_wait<0>();
      if (tx == 0) TS(11);
      float o[32];
      {
        const uint32_t mine = sb + OFF_X + wg * SLOT + tid * 16, other = sb + OFF_X + (wg ^ 1) * SLOT + tid * 16;
        if (wg == 0) {
          #pragma unroll
          for (int i = 0; i < 8; i++) sts128f(mine + i * 2048, acc1[32 + 4 * i], acc1[33 + 4 * i], acc1[34 + 4 * i], acc1[35 + 4 * i]);
          #pragma unroll
          for (int i = 0; i < 32; i++) o[i] = acc1[i];
        } else {
          #pragma unroll
          for (int i = 0; i < 8; i++) sts128f(mine + i * 2048, acc1[4 * i], acc1[4 * i + 1], acc1[4 * i + 2], acc1[4 * i + 3]);
          #pragma unroll
          for (int i = 0; i < 32; i++) o[i] = acc1[32 + i];
        }
        bar_sync(3, 256);
        #pragma unroll
        for (int i = 0; i < 8; i++) { float4 v = lds128f(other + i * 2048); o[4 * i] += v.x; o[4 * i + 1] += v.y; o[4 * i + 2] += v.z; o[4 * i + 3] += v.w; }
      }
      mbar_wait(sb + B_XE, 0, tstart);
      {
        const int tl = wg * 64 + (lane >> 4) * 8 + (lane & 7);
        const uint32_t xa = sb + OFF_X + 6 * SLOT + tl * 128 + (((2 * w + ((lane >> 3) & 1)) ^ (tl & 7)) * 16);
        #pragma unroll
        for (int J2 = 0; J2 < 4; J2++) {
          uint32_t xr[4], res[4];
          ldsm_x4_t(xa + J2 * 2048, xr[0], xr[1], xr[2], xr[3]);
          #pragma unroll
          for (int jj = 0; jj < 2; jj++) {
            const int J = 2 * J2 + jj;
            float4 st = lds128f(sb + OFF_XS + (wg * 64 + J * 8 + 2 * q) * 8);
            const uint32_t mm = pack_bf16(st.x, st.z);
            #pragma unroll
            for (int h = 0; h < 2; h++) {
              uint32_t xx = xr[2 * jj + h];
              uint32_t dx = bsub2(xx, mm);
              uint32_t xn = pack_bf16(bf_lo(dx) * st.y, bf_hi(dx) * st.w);
              const uint32_t* y0 = reinterpret_cast<const uint32_t*>(&yv[h][0]);
              const uint32_t* y1 = reinterpret_cast<const uint32_t*>(&yv[h][1]);
              uint32_t yy = __byte_perm(y0[J >> 1], y1[J >> 1], (J & 1) ? 0x7632 : 0x5410);
              uint32_t kk = __byte_perm(kvw[h][J], 0, 0x1032);
              uint32_t yt = badd2(yy, bmul2(kk, h ? dd1 : dd0));
              uint32_t sv = bmul2(xn, yt);
              uint32_t gt = pack_bf16(silu_f(o[4 * J + 2 * h]), silu_f(o[4 * J + 2 * h + 1]));
              res[2 * jj + h] = badd2(xx, bmul2(sv, gt));
            }
          }
          stsm_x4_t(xa + J2 * 2048, res[0], res[1], res[2], res[3]);
        }
      }
      fence_async_smem();
      bar_sync(1 + wg, 128);
      if (lead) {
        tma_store_2d(&tmOut, sb + OFF_X + 6 * SLOT + wg * 8192, 64 * j, tb * 128 + wg * 64);
        asm volatile("cp.async.bulk.commit_group;" ::: "memory");
        if (wg == 0) g_epoch[bid] = tag;
        asm volatile("cp.async.bulk.wait_group.read 0;" ::: "memory");
        if (wg == 0) { TS(12); TG(41); TDUMP(); }
      }
    } else if (wg == 3) {
      asm volatile("setmaxnreg.dec.sync.aligned.u32 104;");
      THREAD_IDS
      const unsigned tag = GET_TAG();
      {
        const uint32_t t6 = tag & 63u;
        uint2* xg = g_xstat + tb * 160;
        if (w < 3) {
          const int ri = tid >> 2, r = min(j + 7 * ri, 127);
          #pragma unroll 1
          for (int pass = 0; pass < 2; pass++) {
            float sa = 0.f, qa = 0.f;
            #pragma unroll 1
            for (int c = pass ? 0 : 6; c < 7; c++) {
              if (pass) mbar_wait(sb + B_UFULL + 8 * c, 0, tstart);
              if (tid == 0) TS(44 + c);
              #pragma unroll
              for (int i = 0; i < 2; i++) {
                uint4 u = lds128(sb + OFF_X + c * SLOT + r * 128 + ((q + 4 * ((i ^ g) & 1)) * 16));
                float f0 = bf_lo(u.x), f1 = bf_hi(u.x), f2 = bf_lo(u.y), f3 = bf_hi(u.y), f4 = bf_lo(u.z), f5 = bf_hi(u.z), f6 = bf_lo(u.w), f7 = bf_hi(u.w);
                sa += ((f0 + f1) + (f2 + f3)) + ((f4 + f5) + (f6 + f7));
                qa += fmaf(f0, f0, fmaf(f1, f1, fmaf(f2, f2, f3 * f3))) + fmaf(f4, f4, fmaf(f5, f5, fmaf(f6, f6, f7 * f7)));
              }
            }
            #pragma unroll
            for (int o = 1; o < 4; o <<= 1) { sa += __shfl_xor_sync(0xffffffffu, sa, o); qa += __shfl_xor_sync(0xffffffffu, qa, o); }
            float mb, rs; ln_scalars(sa, qa, 1.0f / 448.0f, mb, rs);
            if (pass && q == 0 && j + 7 * ri < 128) st_relaxed64(xg + j * 20 + ri, make_uint2(tag_enc(mb, t6), tag_enc(rs, t6)));
            if (tid == 0) TS(39);
          }
        } else {
          mbar_wait(sb + B_UFULL + 8 * 6, 0, tstart);
          uint2 v[4];
          while (true) {
            uint32_t bad = 0;
            #pragma unroll
            for (int i = 0; i < 4; i++) { const int row = lane + 32 * i; v[i] = ld_relaxed64(xg + (row % 7) * 20 + row / 7); }
            #pragma unroll
            for (int i = 0; i < 4; i++) bad |= (v[i].x ^ t6) | (v[i].y ^ t6);
            if (__all_sync(0xffffffffu, (bad & 63u) == 0) || timed_out(tstart)) break;
          }
          #pragma unroll
          for (int i = 0; i < 4; i++) sts64f(sb + OFF_XS + (lane + 32 * i) * 8, tag_val(v[i].x), tag_val(v[i].y));
          __syncwarp();
          if (lane == 0) { mbar_arrive(sb + B_W1); TS(28); }
        }
      }
      if (j >= 3) {
        if (tid == 0) {
          mbar_wait(sb + B_W1, 0, tstart);
          tma_prefetch_2d(&tmK2, 64 * j, tb * 128); tma_prefetch_2d(&tmV, 64 * j, tb * 128);
          mbar_wait(sb + B_WFULL + 8, 0, tstart);
          mbar_wait(sb + B_EMPTY, 1, tstart); mbar_wait(sb + B_EMPTY + 8, 1, tstart);
          mbar_expect_tx(sb + B_KVT, 2 * SLOT);
          tma_load_2d(sb + OFF_X, &tmK2, sb + B_KVT, 64 * j, tb * 128);
          tma_load_2d(sb + OFF_X + SLOT, &tmV, sb + B_KVT, 64 * j, tb * 128);
        }
        __syncwarp();
        kv_tile(P, tb, j, tid, sb + OFF_X, sb + OFF_X + SLOT, sb + B_KVT, sb + B_KVRD, sb + B_ZOUT, tstart);
        bar_sync(6, 128);
        if (tid == 0) { mbar_arrive(sb + B_KV); fence_async_global(); st_release(g_kvflag + (j * 16 + tb) * FS, tag); TS(24); }
      } else if (tid == 0) {
        while (ld_relaxed32(g_kvflag + (j * 16 + tb) * FS) != tag) { if (timed_out(tstart)) break; }
        fence_acq(); mbar_arrive(sb + B_KV); TS(24);
      }
      __syncwarp();
      if (w == 0) {
        bool done = false;
        while (!done) {
          unsigned v0 = ld_relaxed32(g_cflag + lane * FS), v1 = (lane < 2 * NCONV - 32) ? ld_relaxed32(g_cflag + (32 + lane) * FS) : tag;
          done = __all_sync(0xffffffffu, v0 == tag && v1 == tag);
          if (timed_out(tstart)) break;
          if (!done) __nanosleep(100);
        }
        fence_acq();
        if (lane == 0) { mbar_arrive(sb + B_Y); TS(26); }
      }
    } else {
      asm volatile("setmaxnreg.dec.sync.aligned.u32 40;");
      THREAD_IDS
      if (w == 0) {
        if (lane == 0) {
          prefetch_tmap(&tmWsp); prefetch_tmap(&tmWout); prefetch_tmap(&tmOut);
          mbar_wait(sb + B_SDONE, 0, tstart);
          mbar_expect_tx(sb + B_FULL + 8 * 6, SLOT);
          tma_load_3d(sb + OFF_W + 6 * SLOT, &tmWin, sb + B_FULL + 8 * 6, 0, 6 * 64, 14 + 2 * j);
          #pragma unroll 1
          for (int c = 0; c < 7; c++) {
            const uint32_t fb = sb + B_WFULL + 8 * c;
            mbar_wait(sb + B_EMPTY + 8 * c, 0, tstart);
            mbar_expect_tx(fb, SLOT);
            tma_load_3d(sb + OFF_W + c * SLOT, &tmWin, fb, 0, c * 64, 2 * j);
          }
          int ia = 0, have = 0;
          #pragma unroll 1
          while (ia < G2S && (ia == 0 || lds_acq(sb + OFF_CNT) == 0)) {
            if (mbar_test(sb + B_EMPTY + 8 * ia, 1) || timed_out(tstart)) {
              mbar_expect_tx(sb + B_FULL + 8 * ia, 2 * SLOT);
              tma_load_2d(sb + OFF_W + ia * SLOT, &tmWsp, sb + B_FULL + 8 * ia, ia * 64, tb * 128);
              ia++;
            }
          }
          int s = 0; uint32_t par = 1;
          #pragma unroll 1
          for (int it = 0; it < 32; it++) {
            const uint32_t fb = sb + B_FULL + 8 * s;
            const int kc = it;
            if (it >= ia) {
              mbar_wait(sb + B_EMPTY + 8 * s, par, tstart);
              mbar_expect_tx(fb, 2 * SLOT);
              tma_load_2d(sb + OFF_W + s * SLOT, &tmWsp, fb, kc * 64, tb * 128);
            }
            wait_count(sb + OFF_CNT, it, have);
            if (it == 0 && j >= 3) mbar_wait(sb + B_KVRD, 0, tstart);
            bulk_load(sb + OFF_X + s * SLOT, g_z2img + (size_t)(j * 32 + kc) * 1024, SLOT, fb);
            if (it == 0) TS(21);
            if (++s == G2S) { s = 0; par ^= 1; }
          }
          #pragma unroll 1
          for (int i = 0; i < 7; i++) {
            const int sl = (i == 0) ? 6 : (i + 1) % 6;
            if (i == 0) mbar_wait(sb + B_EMPTY + 8 * 6, 1, tstart);
            else mbar_wait(sb + B_EMPTY + 8 * sl, (sl >= 2) ? 0 : 1, tstart);
            mbar_expect_tx(sb + B_WFULL + 8 * sl, SLOT);
            tma_load_2d(sb + OFF_W + sl * SLOT, &tmWout, sb + B_WFULL + 8 * sl, 64 * j, sl * 128);
            if (sl == 6) { mbar_expect_tx(sb + B_XE, SLOT); tma_load_2d(sb + OFF_X + 6 * SLOT, &tmX, sb + B_XE, 64 * j, tb * 128); }
          }
          have = 0;
          int us = 2;
          #pragma unroll 1
          for (int i = 0; i < 12; i++) {
            const int jj = (i >> 1) + ((i >> 1) >= j);
            if (i >= 4) mbar_wait(sb + B_UEMPTY + 8 * (i - 4), 0, tstart);
            wait_count(sb + OFF_CNT + 4, jj, have);
            mbar_expect_tx(sb + B_UFULL + 8 * i, SLOT);
            bulk_load(sb + OFF_X + us * SLOT, g_uimg + (size_t)(tb * 14 + 2 * jj + (i & 1)) * 1024, SLOT, sb + B_UFULL + 8 * i);
            if (i == 0) TS(22);
            if (++us == 6) us = 0;
          }
        }
      } else {
        uint32_t tag = 0, t6 = 0;
        uint32_t* pub = reinterpret_cast<uint32_t*>(g_w1) + ((j * 2 + (2 - w)) * 8 + (tb >> 1)) * 128 + (tb & 1) * 64;
        if (w == 1) {
          #pragma unroll 1
          for (int pass = 0; pass < 2; pass++) {
            if (pass) { tag = GET_TAG(); t6 = tag & 63u; mbar_wait(sb + B_SFULL, 0, tstart); if (lane == 0) TS(27); }
            float a0 = 0.f, a1 = 0.f, b0 = 0.f, b1 = 0.f;
            #pragma unroll
            for (int i = 0; i < 56; i += 2) {
              const uint32_t u = lds32(sb + OFF_SW + i * 128 + lane * 4), v = lds32(sb + OFF_SW + i * 128 + 128 + lane * 4);
              a0 += bf_lo(u); a1 += bf_hi(u); b0 += bf_lo(v); b1 += bf_hi(v);
            }
            if (pass) { st_relaxed64(pub + lane * 2, make_uint2(tag_enc(a0 + b0, t6), tag_enc(a1 + b1, t6))); __syncwarp(); if (lane == 0) { mbar_arrive(sb + B_SDONE); TS(14); } }
          }
        } else {
          tag = GET_TAG(); t6 = tag & 63u;
          if (w == 2) {
            mbar_wait(sb + B_FULL + 8 * 6, 0, tstart);
            const uint32_t* wp = reinterpret_cast<const uint32_t*>(P.w_in + (size_t)((tb >> 1) * 56) * 1792 + 128 * j + (tb & 1) * 64) + lane;
            float a0 = 0.f, a1 = 0.f;
            #pragma unroll 1
            for (int c = 0; c < 4; c++) {
              uint32_t u[14];
              #pragma unroll
              for (int i = 0; i < 14; i++) u[i] = __ldg(wp + (c * 14 + i) * 896);
              #pragma unroll
              for (int i = 0; i < 14; i++) { a0 += bf_lo(u[i]); a1 += bf_hi(u[i]); }
            }
            st_relaxed64(pub + lane * 2, make_uint2(tag_enc(a0, t6), tag_enc(a1, t6)));
            if (lane == 0) TS(13);
          }
        }
        if (w != 2) {
          #pragma unroll 1
          for (int h = 1; h >= 0; h--) {
            const uint2* p = reinterpret_cast<const uint2*>(g_w1) + (j * 2 + h) * 8 * 64 + (w >> 1) * 32 + lane;
            uint2 v[8];
            while (true) {
              uint32_t bad = 0;
              #pragma unroll
              for (int i = 0; i < 8; i++) v[i] = ld_relaxed64(p + 64 * i);
              #pragma unroll
              for (int i = 0; i < 8; i++) bad |= (v[i].x ^ t6) | (v[i].y ^ t6);
              if (__all_sync(0xffffffffu, (bad & 63u) == 0) || timed_out(tstart)) break;
            }
            float a = 0.f, b = 0.f;
            #pragma unroll
            for (int i = 0; i < 8; i++) { a += tag_val(v[i].x); b += tag_val(v[i].y); }
            sts64f(sb + OFF_W1 + (h * 64 + (w >> 1) * 32 + lane) * 8, a, b);
            __syncwarp();
            if (lane == 0) mbar_arrive(sb + (h ? B_W1 : B_W1B));
            if (tid == 32 && h) TS(25);
          }
          if (lane == 0) {
            const int g2 = w >> 1;
            mbar_wait(sb + B_ZST + 8 * g2, 0, tstart);
            fence_async_global();
            st_release(g_z2flag + (j * 32 + 2 * tb + g2) * FS, tag);
            mbar_arrive(sb + B_ZOUT);
            TS(g2 ? 63 : 5);
            if (g2 == 0) {
              mbar_wait(sb + B_UPUB, 0, tstart);
              fence_async_global();
              st_release(g_uflag + (tb * 8 + j) * FS, tag);
              TS(9);
            }
          }
        } else {
          watch_flags(g_z2flag + j * 32 * FS, 32, tag, sb + OFF_CNT, lane, tstart);
          mbar_wait(sb + B_WFULL + 8 * 5, 1, tstart);
          watch_flags(g_uflag + tb * 8 * FS, 7, tag, sb + OFF_CNT + 4, lane, tstart);
        }
      }
    }
  }
}

typedef CUresult (*PFN_encodeTiled)(CUtensorMap*, CUtensorMapDataType, cuuint32_t, void*, const cuuint64_t*, const cuuint64_t*, const cuuint32_t*,
                                    const cuuint32_t*, CUtensorMapInterleave, CUtensorMapSwizzle, CUtensorMapL2promotion, CUtensorMapFloatOOBfill);

CUtensorMap make_tm(PFN_encodeTiled enc, const void* ptr, uint64_t rows, uint64_t cols, uint32_t brows, uint32_t bcols) {
  CUtensorMap tm;
  cuuint64_t gd[2] = {cols, rows}; cuuint64_t gs[1] = {cols * 2}; cuuint32_t bd[2] = {bcols, brows}; cuuint32_t es[2] = {1, 1};
  enc(&tm, CU_TENSOR_MAP_DATA_TYPE_BFLOAT16, 2, const_cast<void*>(ptr), gd, gs, bd, es, CU_TENSOR_MAP_INTERLEAVE_NONE, CU_TENSOR_MAP_SWIZZLE_128B,
      CU_TENSOR_MAP_L2_PROMOTION_L2_256B, CU_TENSOR_MAP_FLOAT_OOB_FILL_NONE);
  return tm;
}

}

extern "C" void kernel_launch(void* const* d_in, const int* in_sizes, int n_in, void* d_out, int out_size) {
  (void)in_sizes; (void)n_in; (void)out_size;
  static PFN_encodeTiled enc = nullptr;
  if (!enc) {
    void* p = nullptr; cudaDriverEntryPointQueryResult qr;
    cudaGetDriverEntryPoint("cuTensorMapEncodeTiled", &p, cudaEnableDefault, &qr);
    enc = (PFN_encodeTiled)p;
    cudaFuncSetAttribute(fused_kernel, cudaFuncAttributeMaxDynamicSharedMemorySize, SMEM_BYTES);
  }
  Params P;
  P.w_in = (const bf16*)d_in[7]; P.pad = nullptr; P.k = (const bf16*)d_in[1]; P.v = (const bf16*)d_in[2]; P.shift_k = (const bf16*)d_in[3];
  P.ssm_k = (const bf16*)d_in[4]; P.ssm_D = (const bf16*)d_in[5]; P.b_sp = (const bf16*)d_in[9];
  CUtensorMap tmX = make_tm(enc, d_in[0], 2048, 448, 128, 64);
  for (int bid = 0; bid < 136; bid++) {
    int tb = -1, j = 0, cidx = 0;
    if (bid < 16) { int r = bid & 7; if (r < 7) { tb = (bid < 8) ? 15 : 0; j = r; } else cidx = bid >> 3; }
    else if (bid < 96) { int gq = (bid - 16) >> 4, r = (bid - 16) & 15; if (r < 14) { tb = 1 + 2 * gq + (r >= 7); j = r % 7; } else cidx = 2 + 2 * gq + (r - 14); }
    else { int gq = (bid - 96) / 18, r = (bid - 96) % 18; if (r < 14) { tb = 11 + 2 * gq + (r >= 7); j = r % 7; } else cidx = 12 + 4 * gq + (r - 14); }
    P.role[bid] = (uint8_t)(tb >= 0 ? tb * 8 + j : 128 + cidx);
  }
  CUtensorMap tmWin, tmWs;
  {
    cuuint64_t gd[3] = {64, 448, 28}; cuuint64_t gs[2] = {3584, 128}; cuuint32_t bd[3] = {64, 64, 2}; cuuint32_t es[3] = {1, 1, 1};
    enc(&tmWin, CU_TENSOR_MAP_DATA_TYPE_BFLOAT16, 3, d_in[7], gd, gs, bd, es, CU_TENSOR_MAP_INTERLEAVE_NONE, CU_TENSOR_MAP_SWIZZLE_128B,
        CU_TENSOR_MAP_L2_PROMOTION_L2_256B, CU_TENSOR_MAP_FLOAT_OOB_FILL_NONE);
    cuuint64_t gd2[2] = {1792, 448}; cuuint64_t gs2[1] = {3584}; cuuint32_t bd2[2] = {64, 56};
    enc(&tmWs, CU_TENSOR_MAP_DATA_TYPE_BFLOAT16, 2, d_in[7], gd2, gs2, bd2, es, CU_TENSOR_MAP_INTERLEAVE_NONE, CU_TENSOR_MAP_SWIZZLE_NONE,
        CU_TENSOR_MAP_L2_PROMOTION_L2_256B, CU_TENSOR_MAP_FLOAT_OOB_FILL_NONE);
  }
  CUtensorMap tmK, tmK2, tmV;
  {
    cuuint64_t gd[2] = {448, 2048}; cuuint64_t gs[1] = {896}; cuuint32_t bk[2] = {64, 136}, bv[2] = {64, 128}; cuuint32_t es[2] = {1, 1};
    enc(&tmK, CU_TENSOR_MAP_DATA_TYPE_BFLOAT16, 2, d_in[1], gd, gs, bk, es, CU_TENSOR_MAP_INTERLEAVE_NONE, CU_TENSOR_MAP_SWIZZLE_NONE,
        CU_TENSOR_MAP_L2_PROMOTION_L2_128B, CU_TENSOR_MAP_FLOAT_OOB_FILL_NONE);
    enc(&tmK2, CU_TENSOR_MAP_DATA_TYPE_BFLOAT16, 2, d_in[1], gd, gs, bv, es, CU_TENSOR_MAP_INTERLEAVE_NONE, CU_TENSOR_MAP_SWIZZLE_NONE,
        CU_TENSOR_MAP_L2_PROMOTION_L2_128B, CU_TENSOR_MAP_FLOAT_OOB_FILL_NONE);
    enc(&tmV, CU_TENSOR_MAP_DATA_TYPE_BFLOAT16, 2, d_in[2], gd, gs, bv, es, CU_TENSOR_MAP_INTERLEAVE_NONE, CU_TENSOR_MAP_SWIZZLE_NONE,
        CU_TENSOR_MAP_L2_PROMOTION_L2_128B, CU_TENSOR_MAP_FLOAT_OOB_FILL_NONE);
  }
  CUtensorMap tmWsp = make_tm(enc, d_in[8], 2048, 2048, 128, 64);
  CUtensorMap tmWout = make_tm(enc, d_in[10], 896, 448, 128, 64);
  CUtensorMap tmOut = make_tm(enc, d_out, 2048, 448, 64, 64);
  fused_kernel<<<132, 512, SMEM_BYTES, cudaStreamPerThread>>>(P, tmX, tmWin, tmWs, tmK, tmV, tmK2, tmWsp, tmWout, tmOut);
}
```
